```python
import torch

def _softmax(x, axis=-1):
    return torch.softmax(x, dim=axis)
def _gelu(x):
    return torch.nn.functional.gelu(x, approximate="tanh")
def _silu(x):
    return torch.nn.functional.silu(x)
def _sigmoid(x):
    return torch.sigmoid(x)
def _layernorm(x, axis=-1, eps=1e-5):
    m = x.mean(dim=axis, keepdim=True)
    v = x.var(dim=axis, keepdim=True, unbiased=False)
    return (x - m) / torch.sqrt(v + eps)
def _scatter_add(tgt, idx, src, axis=0):
    return tgt.clone().index_add_(axis, idx, src)
def _segment_sum(src, seg, n):
    out = torch.zeros((n,) + src.shape[1:], dtype=src.dtype)
    return out.index_add_(0, seg, src)
def _pad(x, pw):
    flat = tuple(v for pair in reversed(pw) for v in pair)
    return torch.nn.functional.pad(x, flat)

kernel_name = 'sequential_preLN__softmax_full_mha__mixer_token_mlp__prompt'

def setup_inputs():

    _w = (lambda a: (lambda t: t.to(torch.bfloat16) if t.is_floating_point() else t)(torch.as_tensor(a)))
    def _A_setup():
        B, S, D = 1, 2048, 640
        return {
            "x": _w((lambda *s: torch.randn(*s, dtype=torch.bfloat16) * 0.05)(B, S, D)),
            "wqkv": _w((lambda *s: torch.randn(*s, dtype=torch.bfloat16) * 0.05)(D, 3 * D)),
            "wo": _w((lambda *s: torch.randn(*s, dtype=torch.bfloat16) * 0.05)(D, D)),
        }
    _A_in = _A_setup()

    def _B_setup():
        B, S, D, F = 1, 2048, 640, 1728
        return {
            "x": _w((lambda *s: torch.randn(*s, dtype=torch.bfloat16) * 0.05)(B, S, D)),
            "w1": _w((lambda *s: torch.randn(*s, dtype=torch.bfloat16) * 1.6)(S, F) * (S ** -0.5)),
            "b1": _w((lambda *s: torch.randn(*s, dtype=torch.bfloat16) * 1.6)(F) * 0.02),
            "w2": _w((lambda *s: torch.randn(*s, dtype=torch.bfloat16) * 0.2)(F, S) * (F ** -0.5)),
            "b2": _w((lambda *s: torch.randn(*s, dtype=torch.bfloat16) * 0.2)(S) * 0.02),
        }
    _B_in = _B_setup()

    return {
        "A_x": _A_in["x"],
        "A_wqkv": _A_in["wqkv"],
        "A_wo": _A_in["wo"],
        "B_x": _B_in["x"],
        "B_w1": _B_in["w1"],
        "B_b1": _B_in["b1"],
        "B_w2": _B_in["w2"],
        "B_b2": _B_in["b2"],
    }

def reference(A_x, A_wqkv, A_wo, B_x, B_w1, B_b1, B_w2, B_b2):
    def _A_ref(x, wqkv, wo):
        B, S, D = x.shape
        H = 32; Dh = D // H
        qkv = (lambda x, *d: x.permute(*d))((x @ wqkv).reshape(B, S, 3, H, Dh), 2, 0, 3, 1, 4)
        q, k, v = qkv[0], qkv[1], qkv[2]
        scale = Dh ** -0.5
        scores = torch.einsum("bhqd,bhkd->bhqk", q, k) * scale
        p = _softmax(scores, axis=-1)
        o = torch.einsum("bhqk,bhkd->bhqd", p, v)
        return (lambda x, *d: x.permute(*d))(o, 0, 2, 1, 3).reshape(B, S, D) @ wo

    def _B_ref(x, w1, b1, w2, b2):
        B, S, D = x.shape
        h = _layernorm(x, axis=-1)
        u = torch.einsum("bsd,sf->bdf", h, w1) + b1
        u = _gelu(u)
        y = torch.einsum("bdf,fs->bds", u, w2) + b2
        return (lambda x, *d: x.permute(*d))(y, 0, 2, 1)

    x = A_x
    h = x + _A_ref(_layernorm(x, axis=-1), A_wqkv, A_wo)
    h2 = h + _B_ref(_layernorm(h, axis=-1), B_w1, B_b1, B_w2, B_b2)
    return h2
```

```cpp
#include <cuda_runtime.h>
#include <cuda.h>
#include <cuda_bf16.h>
#include <stdint.h>

namespace {

constexpr int S = 2048, D = 640, H = 32, F = 1728, N3 = 1920;
constexpr float LN_EPS = 1e-5f;
constexpr int SPIN_LIMIT = 1 << 22;

__device__ __align__(1024) uint8_t g_q[H * 32 * 3 * 1024];
__device__ __align__(1024) uint8_t g_kv[H * 32 * 6 * 1024];
__device__ __align__(16) float g_kn2[H * 128];
__device__ __align__(1024) uint8_t g_o[32 * 80 * 1024];
__device__ __align__(1024) uint8_t g_wo[4 * 80 * 2560];
__device__ __align__(1024) uint8_t g_hn[4 * 256 * 2560];
__device__ __align__(1024) uint8_t g_g[4 * 216 * 2560];
__device__ __align__(16) uint2 g_ln1[S];
__device__ __align__(16) uint32_t g_cs[16 * N3];
__device__ __align__(128) int g_cnt[256];
__device__ __align__(128) uint2 g_ln2[S * 8];

#define STAMP(k, slot, cond)
__device__ __forceinline__ uint32_t smem_u32(const void* p) { return (uint32_t)__cvta_generic_to_shared(p); }
__device__ __forceinline__ void mbar_init(uint32_t bar, int cnt) { asm volatile("mbarrier.init.shared::cta.b64 [%0], %1;" :: "r"(bar), "r"(cnt)); }
__device__ __forceinline__ void mbar_expect_tx(uint32_t bar, uint32_t bytes) { asm volatile("mbarrier.arrive.expect_tx.shared::cta.b64 _, [%0], %1;" :: "r"(bar), "r"(bytes) : "memory"); }
__device__ __forceinline__ void mbar_arrive(uint32_t bar) { asm volatile("mbarrier.arrive.shared::cta.b64 _, [%0];" :: "r"(bar) : "memory"); }
__device__ __forceinline__ void mbar_wait(uint32_t bar, uint32_t parity) {
    asm volatile("{\n.reg .pred p;\n.reg .u32 c;\nmov.u32 c, 0;\nWAIT_%=:\n"
                 "mbarrier.try_wait.parity.shared::cta.b64 p, [%0], %1;\n@p bra DONE_%=;\n"
                 "add.u32 c, c, 1;\nsetp.lt.u32 p, c, 0x400000;\n@p bra WAIT_%=;\nDONE_%=:\n}\n" :: "r"(bar), "r"(parity) : "memory");
}
__device__ __forceinline__ void fence_mbar_init() { asm volatile("fence.mbarrier_init.release.cluster;" ::: "memory"); }
__device__ __forceinline__ void fence_async_smem() { asm volatile("fence.proxy.async.shared::cta;" ::: "memory"); }
__device__ __forceinline__ void bulk_load(uint32_t dst, const void* src, uint32_t bytes, uint32_t bar) {
    asm volatile("cp.async.bulk.shared::cluster.global.mbarrier::complete_tx::bytes [%0], [%1], %2, [%3];" :: "r"(dst), "l"(src), "r"(bytes), "r"(bar) : "memory");
}
__device__ __forceinline__ void sts32(uint32_t addr, uint32_t v) { asm volatile("st.shared.b32 [%0], %1;" :: "r"(addr), "r"(v) : "memory"); }
__device__ __forceinline__ void tma2d(uint32_t dst, const CUtensorMap* tm, int c0, int c1, uint32_t bar) {
    asm volatile("cp.async.bulk.tensor.2d.shared::cluster.global.mbarrier::complete_tx::bytes [%0], [%1, {%3, %4}], [%2];" :: "r"(dst), "l"(tm), "r"(bar), "r"(c0), "r"(c1) : "memory");
}
__device__ __forceinline__ void tma2d_store(const CUtensorMap* tm, uint32_t src, int c0, int c1) {
    asm volatile("cp.async.bulk.tensor.2d.global.shared::cta.bulk_group [%0, {%2, %3}], [%1];" :: "l"(tm), "r"(src), "r"(c0), "r"(c1) : "memory");
}
__device__ __forceinline__ void prefetch_tmap(const CUtensorMap* tm) { asm volatile("prefetch.tensormap [%0];" :: "l"(tm) : "memory"); }
__device__ __forceinline__ void l2_prefetch(const void* p, uint32_t bytes) { asm volatile("cp.async.bulk.prefetch.L2.global [%0], %1;" :: "l"(p), "r"(bytes) : "memory"); }
__device__ __forceinline__ bool elect_one() {
    uint32_t pred;
    asm volatile("{\n.reg .pred p;\nelect.sync _|p, 0xffffffff;\nselp.u32 %0, 1, 0, p;\n}\n" : "=r"(pred));
    return pred != 0;
}
__device__ __forceinline__ void pdl_wait() { asm volatile("griddepcontrol.wait;" ::: "memory"); }
__device__ __forceinline__ void pdl_launch() { asm volatile("griddepcontrol.launch_dependents;" ::: "memory"); }
__device__ __forceinline__ void bar_sync(int id, int n) { asm volatile("bar.sync %0, %1;" :: "r"(id), "r"(n) : "memory"); }
__device__ __forceinline__ void bar_arrive(int id, int n) { asm volatile("bar.arrive %0, %1;" :: "r"(id), "r"(n) : "memory"); }
__device__ __forceinline__ void wg_fence() { asm volatile("wgmma.fence.sync.aligned;" ::: "memory"); }
__device__ __forceinline__ void wg_commit() { asm volatile("wgmma.commit_group.sync.aligned;" ::: "memory"); }
template <int N> __device__ __forceinline__ void wg_wait() { asm volatile("wgmma.wait_group.sync.aligned %0;" :: "n"(N) : "memory"); }
__device__ __forceinline__ float ex2f(float x) { float y; asm("ex2.approx.ftz.f32 %0, %1;" : "=f"(y) : "f"(x)); return y; }
__device__ __forceinline__ float sqrt_fast(float x) { float y; asm("sqrt.approx.f32 %0, %1;" : "=f"(y) : "f"(x)); return y; }
__device__ __forceinline__ float tanhf_fast(float x) { float y; asm("tanh.approx.f32 %0, %1;" : "=f"(y) : "f"(x)); return y; }
__device__ __forceinline__ uint32_t pack_bf16(float lo, float hi) { uint32_t r; asm("cvt.rn.bf16x2.f32 %0, %1, %2;" : "=r"(r) : "f"(hi), "f"(lo)); return r; }
__device__ __forceinline__ float bf_lo(uint32_t v) { return __uint_as_float(v << 16); }
__device__ __forceinline__ float bf_hi(uint32_t v) { return __uint_as_float(v & 0xffff0000u); }
__device__ __forceinline__ uint32_t hfma2(uint32_t a, uint32_t b, uint32_t c) { uint32_t r; asm("fma.rn.bf16x2 %0, %1, %2, %3;" : "=r"(r) : "r"(a), "r"(b), "r"(c)); return r; }
__device__ __forceinline__ uint64_t desc_from(uint32_t lo, uint32_t hi) { uint64_t d; asm("mov.b64 %0, {%1, %2};" : "=l"(d) : "r"(lo), "r"(hi)); return d; }
__device__ __forceinline__ void desc_adv(uint64_t& d, uint32_t step) {
    asm("{\n.reg .b32 lo, hi;\nmov.b64 {lo, hi}, %0;\nadd.u32 lo, lo, %1;\nmov.b64 %0, {lo, hi};\n}\n" : "+l"(d) : "r"(step));
}
template <int N> __device__ __forceinline__ void fence_regs(float (&d)[N]) {
#pragma unroll
    for (int i = 0; i < N; i++) asm volatile("" : "+f"(d[i]) :: "memory");
}
template <int N> __device__ __forceinline__ void fence_regs(uint32_t (&d)[N]) {
#pragma unroll
    for (int i = 0; i < N; i++) asm volatile("" : "+r"(d[i]) :: "memory");
}
__device__ __forceinline__ int ld_acquire(const int* p) { int v; asm volatile("ld.acquire.gpu.global.b32 %0, [%1];" : "=r"(v) : "l"(p) : "memory"); return v; }
__device__ __forceinline__ void st_relaxed_v2(uint2* p, uint32_t a, uint32_t b) { uint64_t v = (uint64_t)a | ((uint64_t)b << 32); asm volatile("st.relaxed.gpu.global.b64 [%0], %1;" :: "l"(p), "l"(v) : "memory"); }

__device__ __forceinline__ uint4 ld_relaxed_v4(const uint32_t* p) {
    uint4 v; asm volatile("ld.relaxed.gpu.global.v4.b32 {%0, %1, %2, %3}, [%4];" : "=r"(v.x), "=r"(v.y), "=r"(v.z), "=r"(v.w) : "l"(p) : "memory"); return v;
}
__device__ __forceinline__ uint4 ld_relaxed_2x64(const uint2* p) {
    uint64_t a, b; asm volatile("ld.relaxed.gpu.global.v2.b64 {%0, %1}, [%2];" : "=l"(a), "=l"(b) : "l"(p) : "memory");
    return make_uint4((uint32_t)a, (uint32_t)(a >> 32), (uint32_t)b, (uint32_t)(b >> 32));
}
__device__ __forceinline__ void st_relaxed_v4(uint32_t* p, uint32_t a, uint32_t b, uint32_t c, uint32_t d) {
    asm volatile("st.relaxed.gpu.global.v4.b32 [%0], {%1, %2, %3, %4};" :: "l"(p), "r"(a), "r"(b), "r"(c), "r"(d) : "memory");
}
__device__ __forceinline__ uint32_t enc_word(float v) { const uint32_t u = ~__float_as_uint(v); return u ? u : 0x80000000u; }
__device__ __forceinline__ float dec_word(uint32_t u) { return __uint_as_float(~u); }

__device__ __forceinline__ void wgmma_ss_n240_ta0_tb1(float (&d)[120], uint64_t descA, uint64_t descB, int scaleD) {
    asm volatile("{\n.reg .pred p;\nsetp.ne.b32 p, %122, 0;\n"
        "wgmma.mma_async.sync.aligned.m64n240k16.f32.bf16.bf16 {%0, %1, %2, %3, %4, %5, %6, %7, %8, %9, %10, %11, %12, %13, %14, %15, %16, %17, %18, %19, %20, %21, %22, %23, %24, %25, %26, %27, %28, %29, %30, %31, %32, %33, %34, %35, %36, %37, %38, %39, %40, %41, %42, %43, %44, %45, %46, %47, %48, %49, %50, %51, %52, %53, %54, %55, %56, %57, %58, %59, %60, %61, %62, %63, %64, %65, %66, %67, %68, %69, %70, %71, %72, %73, %74, %75, %76, %77, %78, %79, %80, %81, %82, %83, %84, %85, %86, %87, %88, %89, %90, %91, %92, %93, %94, %95, %96, %97, %98, %99, %100, %101, %102, %103, %104, %105, %106, %107, %108, %109, %110, %111, %112, %113, %114, %115, %116, %117, %118, %119}, %120, %121, p, 1, 1, 0, 1;\n}\n"
        : "+f"(d[0]), "+f"(d[1]), "+f"(d[2]), "+f"(d[3]), "+f"(d[4]), "+f"(d[5]), "+f"(d[6]), "+f"(d[7]), "+f"(d[8]), "+f"(d[9]), "+f"(d[10]), "+f"(d[11]), "+f"(d[12]), "+f"(d[13]), "+f"(d[14]), "+f"(d[15]), "+f"(d[16]), "+f"(d[17]), "+f"(d[18]), "+f"(d[19]), "+f"(d[20]), "+f"(d[21]), "+f"(d[22]), "+f"(d[23]), "+f"(d[24]), "+f"(d[25]), "+f"(d[26]), "+f"(d[27]), "+f"(d[28]), "+f"(d[29]), "+f"(d[30]), "+f"(d[31]), "+f"(d[32]), "+f"(d[33]), "+f"(d[34]), "+f"(d[35]), "+f"(d[36]), "+f"(d[37]), "+f"(d[38]), "+f"(d[39]), "+f"(d[40]), "+f"(d[41]), "+f"(d[42]), "+f"(d[43]), "+f"(d[44]), "+f"(d[45]), "+f"(d[46]), "+f"(d[47]), "+f"(d[48]), "+f"(d[49]), "+f"(d[50]), "+f"(d[51]), "+f"(d[52]), "+f"(d[53]), "+f"(d[54]), "+f"(d[55]), "+f"(d[56]), "+f"(d[57]), "+f"(d[58]), "+f"(d[59]), "+f"(d[60]), "+f"(d[61]), "+f"(d[62]), "+f"(d[63]), "+f"(d[64]), "+f"(d[65]), "+f"(d[66]), "+f"(d[67]), "+f"(d[68]), "+f"(d[69]), "+f"(d[70]), "+f"(d[71]), "+f"(d[72]), "+f"(d[73]), "+f"(d[74]), "+f"(d[75]), "+f"(d[76]), "+f"(d[77]), "+f"(d[78]), "+f"(d[79]), "+f"(d[80]), "+f"(d[81]), "+f"(d[82]), "+f"(d[83]), "+f"(d[84]), "+f"(d[85]), "+f"(d[86]), "+f"(d[87]), "+f"(d[88]), "+f"(d[89]), "+f"(d[90]), "+f"(d[91]), "+f"(d[92]), "+f"(d[93]), "+f"(d[94]), "+f"(d[95]), "+f"(d[96]), "+f"(d[97]), "+f"(d[98]), "+f"(d[99]), "+f"(d[100]), "+f"(d[101]), "+f"(d[102]), "+f"(d[103]), "+f"(d[104]), "+f"(d[105]), "+f"(d[106]), "+f"(d[107]), "+f"(d[108]), "+f"(d[109]), "+f"(d[110]), "+f"(d[111]), "+f"(d[112]), "+f"(d[113]), "+f"(d[114]), "+f"(d[115]), "+f"(d[116]), "+f"(d[117]), "+f"(d[118]), "+f"(d[119])
        : "l"(descA), "l"(descB), "r"(scaleD));
}
__device__ __forceinline__ void wgmma_ss_n80_ta0_tb1(float (&d)[40], uint64_t descA, uint64_t descB, int scaleD) {
    asm volatile("{\n.reg .pred p;\nsetp.ne.b32 p, %42, 0;\n"
        "wgmma.mma_async.sync.aligned.m64n80k16.f32.bf16.bf16 {%0, %1, %2, %3, %4, %5, %6, %7, %8, %9, %10, %11, %12, %13, %14, %15, %16, %17, %18, %19, %20, %21, %22, %23, %24, %25, %26, %27, %28, %29, %30, %31, %32, %33, %34, %35, %36, %37, %38, %39}, %40, %41, p, 1, 1, 0, 1;\n}\n"
        : "+f"(d[0]), "+f"(d[1]), "+f"(d[2]), "+f"(d[3]), "+f"(d[4]), "+f"(d[5]), "+f"(d[6]), "+f"(d[7]), "+f"(d[8]), "+f"(d[9]), "+f"(d[10]), "+f"(d[11]), "+f"(d[12]), "+f"(d[13]), "+f"(d[14]), "+f"(d[15]), "+f"(d[16]), "+f"(d[17]), "+f"(d[18]), "+f"(d[19]), "+f"(d[20]), "+f"(d[21]), "+f"(d[22]), "+f"(d[23]), "+f"(d[24]), "+f"(d[25]), "+f"(d[26]), "+f"(d[27]), "+f"(d[28]), "+f"(d[29]), "+f"(d[30]), "+f"(d[31]), "+f"(d[32]), "+f"(d[33]), "+f"(d[34]), "+f"(d[35]), "+f"(d[36]), "+f"(d[37]), "+f"(d[38]), "+f"(d[39])
        : "l"(descA), "l"(descB), "r"(scaleD));
}
__device__ __forceinline__ void wgmma_ss_n80_ta1_tb1(float (&d)[40], uint64_t descA, uint64_t descB, int scaleD) {
    asm volatile("{\n.reg .pred p;\nsetp.ne.b32 p, %42, 0;\n"
        "wgmma.mma_async.sync.aligned.m64n80k16.f32.bf16.bf16 {%0, %1, %2, %3, %4, %5, %6, %7, %8, %9, %10, %11, %12, %13, %14, %15, %16, %17, %18, %19, %20, %21, %22, %23, %24, %25, %26, %27, %28, %29, %30, %31, %32, %33, %34, %35, %36, %37, %38, %39}, %40, %41, p, 1, 1, 1, 1;\n}\n"
        : "+f"(d[0]), "+f"(d[1]), "+f"(d[2]), "+f"(d[3]), "+f"(d[4]), "+f"(d[5]), "+f"(d[6]), "+f"(d[7]), "+f"(d[8]), "+f"(d[9]), "+f"(d[10]), "+f"(d[11]), "+f"(d[12]), "+f"(d[13]), "+f"(d[14]), "+f"(d[15]), "+f"(d[16]), "+f"(d[17]), "+f"(d[18]), "+f"(d[19]), "+f"(d[20]), "+f"(d[21]), "+f"(d[22]), "+f"(d[23]), "+f"(d[24]), "+f"(d[25]), "+f"(d[26]), "+f"(d[27]), "+f"(d[28]), "+f"(d[29]), "+f"(d[30]), "+f"(d[31]), "+f"(d[32]), "+f"(d[33]), "+f"(d[34]), "+f"(d[35]), "+f"(d[36]), "+f"(d[37]), "+f"(d[38]), "+f"(d[39])
        : "l"(descA), "l"(descB), "r"(scaleD));
}
__device__ __forceinline__ void wgmma_rs_n64_tb0(float (&d)[32], uint32_t a0, uint32_t a1, uint32_t a2, uint32_t a3, uint64_t descB, int scaleD) {
    asm volatile("{\n.reg .pred p;\nsetp.ne.b32 p, %37, 0;\n"
        "wgmma.mma_async.sync.aligned.m64n64k16.f32.bf16.bf16 {%0, %1, %2, %3, %4, %5, %6, %7, %8, %9, %10, %11, %12, %13, %14, %15, %16, %17, %18, %19, %20, %21, %22, %23, %24, %25, %26, %27, %28, %29, %30, %31}, {%32, %33, %34, %35}, %36, p, 1, 1, 0;\n}\n"
        : "+f"(d[0]), "+f"(d[1]), "+f"(d[2]), "+f"(d[3]), "+f"(d[4]), "+f"(d[5]), "+f"(d[6]), "+f"(d[7]), "+f"(d[8]), "+f"(d[9]), "+f"(d[10]), "+f"(d[11]), "+f"(d[12]), "+f"(d[13]), "+f"(d[14]), "+f"(d[15]), "+f"(d[16]), "+f"(d[17]), "+f"(d[18]), "+f"(d[19]), "+f"(d[20]), "+f"(d[21]), "+f"(d[22]), "+f"(d[23]), "+f"(d[24]), "+f"(d[25]), "+f"(d[26]), "+f"(d[27]), "+f"(d[28]), "+f"(d[29]), "+f"(d[30]), "+f"(d[31])
        : "r"(a0), "r"(a1), "r"(a2), "r"(a3), "l"(descB), "r"(scaleD));
}
__device__ __forceinline__ void wgmma_rs_n24_tb1(float (&d)[12], uint32_t a0, uint32_t a1, uint32_t a2, uint32_t a3, uint64_t descB, int scaleD) {
    asm volatile("{\n.reg .pred p;\nsetp.ne.b32 p, %17, 0;\n"
        "wgmma.mma_async.sync.aligned.m64n24k16.f32.bf16.bf16 {%0, %1, %2, %3, %4, %5, %6, %7, %8, %9, %10, %11}, {%12, %13, %14, %15}, %16, p, 1, 1, 1;\n}\n"
        : "+f"(d[0]), "+f"(d[1]), "+f"(d[2]), "+f"(d[3]), "+f"(d[4]), "+f"(d[5]), "+f"(d[6]), "+f"(d[7]), "+f"(d[8]), "+f"(d[9]), "+f"(d[10]), "+f"(d[11])
        : "r"(a0), "r"(a1), "r"(a2), "r"(a3), "l"(descB), "r"(scaleD));
}

constexpr uint32_t DESC_SW128 = (1024 >> 4) | (1u << 30);
constexpr uint32_t POLYMASK = 0xB5;

constexpr int K1_ST = 4, K1_STB = 16384 + 32768;
constexpr int K1_SMEM = K1_ST * K1_STB + 1024;

__global__ void __launch_bounds__(384, 1) qkv_kernel(const __grid_constant__ CUtensorMap tmX, const __grid_constant__ CUtensorMap tmW,
                                                     const __nv_bfloat16* __restrict__ x, const __nv_bfloat16* __restrict__ wqkv) {
    extern __shared__ uint8_t smem_raw[];
    __shared__ __align__(8) uint64_t bars[2 * K1_ST];
    __shared__ __align__(16) float2 s_stat[128];
    __shared__ __align__(16) float s_cs[240];
    const uint32_t sbase = (smem_u32(smem_raw) + 1023) & ~1023u;
    const uint32_t full = smem_u32(bars), empty = full + 8 * K1_ST;
    const int tid = threadIdx.x, wg = __shfl_sync(~0u, tid >> 7, 0), warp = __shfl_sync(~0u, (tid >> 5) & 3, 0), lane = tid & 31;
    const int b = blockIdx.x, mb = (b >> 1) & 15, nb = ((b >> 5) << 1) + (b & 1);
    STAMP(0, 0, tid == 0);
    if (wg == 2 && warp == 0) {
        if (elect_one()) {
            for (int i = 0; i < K1_ST; i++) { mbar_init(full + 8 * i, 1); mbar_init(empty + 8 * i, 2); }
            fence_mbar_init();
            fence_async_smem();
#pragma unroll 1
            for (int kb = 0; kb < K1_ST; kb++) {
                const uint32_t sa = sbase + kb * K1_STB, fb = full + 8 * kb;
                mbar_expect_tx(fb, K1_STB);
                tma2d(sa, &tmX, kb * 64, mb * 128, fb);
#pragma unroll
                for (int i = 0; i < 4; i++) tma2d(sa + 16384 + i * 8192, &tmW, nb * 240 + i * 64, kb * 64, fb);
            }
        }
        __syncwarp();
    }
    __syncthreads();
    pdl_launch();
    if (wg == 2) {
        if (warp == 0) {
            if (elect_one()) {
                int st = 0, ph = 0;
#pragma unroll 1
                for (int kb = K1_ST; kb < 10; kb++) {
                    mbar_wait(empty + 8 * st, ph);
                    const uint32_t sa = sbase + st * K1_STB, fb = full + 8 * st;
                    mbar_expect_tx(fb, K1_STB);
                    tma2d(sa, &tmX, kb * 64, mb * 128, fb);
#pragma unroll
                    for (int i = 0; i < 4; i++) tma2d(sa + 16384 + i * 8192, &tmW, nb * 240 + i * 64, kb * 64, fb);
                    if (++st == K1_ST) { st = 0; ph ^= 1; }
                }
            }
        } else {
            const int at = tid - 288;
            if (warp < 3) {
                const int hl = at & 15, rg = at >> 4;
                const uint4* px = reinterpret_cast<const uint4*>(x + (size_t)(mb * 128 + nb * 16 + rg * 4) * D) + hl;
                uint4 v[4][5];
#pragma unroll
                for (int r = 0; r < 4; r++)
#pragma unroll
                    for (int i = 0; i < 5; i++) v[r][i] = __ldg(px + r * 80 + 16 * i);
#pragma unroll
                for (int r = 0; r < 4; r++) {
                    float s = 0.f, q = 0.f;
#pragma unroll
                    for (int i = 0; i < 5; i++) {
                        const uint32_t w[4] = {v[r][i].x, v[r][i].y, v[r][i].z, v[r][i].w};
#pragma unroll
                        for (int c = 0; c < 4; c++) { const float a = bf_lo(w[c]), e = bf_hi(w[c]); s += a + e; q = fmaf(a, a, fmaf(e, e, q)); }
                    }
#pragma unroll
                    for (int o = 8; o; o >>= 1) { s += __shfl_xor_sync(~0u, s, o); q += __shfl_xor_sync(~0u, q, o); }
                    const float mean = s * (1.f / D);
                    const float rstd = rsqrtf(fmaxf(q * (1.f / D) - mean * mean, 0.f) + LN_EPS);
                    if (hl == 0) st_relaxed_v2(&g_ln1[mb * 128 + nb * 16 + rg * 4 + r], enc_word(mean), enc_word(rstd));
                }
            } else if (lane < 30) {
                const uint4* pw = reinterpret_cast<const uint4*>(wqkv + (size_t)(mb * 40) * N3 + nb * 240) + lane;
                float a[8];
#pragma unroll
                for (int c = 0; c < 8; c++) a[c] = 0.f;
#pragma unroll 1
                for (int k0 = 0; k0 < 40; k0 += 20) {
                    uint4 v[20];
#pragma unroll
                    for (int k = 0; k < 20; k++) v[k] = __ldg(pw + (size_t)(k0 + k) * (N3 / 8));
#pragma unroll
                    for (int k = 0; k < 20; k++) {
                        a[0] += bf_lo(v[k].x); a[1] += bf_hi(v[k].x); a[2] += bf_lo(v[k].y); a[3] += bf_hi(v[k].y);
                        a[4] += bf_lo(v[k].z); a[5] += bf_hi(v[k].z); a[6] += bf_lo(v[k].w); a[7] += bf_hi(v[k].w);
                    }
                }
                uint32_t* pc = g_cs + mb * N3 + nb * 240 + lane * 8;
                st_relaxed_v4(pc, enc_word(a[0]), enc_word(a[1]), enc_word(a[2]), enc_word(a[3]));
                st_relaxed_v4(pc + 4, enc_word(a[4]), enc_word(a[5]), enc_word(a[6]), enc_word(a[7]));
            }
            STAMP(0, 3, at == 0);
            if (at < 64) *reinterpret_cast<uint4*>(&g_ln2[b * 128 + at * 2]) = make_uint4(0u, 0u, 0u, 0u);
            if (at == 64 && b < 8) g_cnt[b * 32] = 0;
            mbar_wait(full + 8 * 2, 1);
            if (at < 60) {
                uint4 v[16];
                for (int it = 0; it < SPIN_LIMIT; it++) {
                    uint32_t ok = 1;
#pragma unroll
                    for (int m = 0; m < 16; m++) v[m] = ld_relaxed_v4(g_cs + m * N3 + nb * 240 + at * 4);
#pragma unroll
                    for (int m = 0; m < 16; m++) ok &= (v[m].x != 0) & (v[m].y != 0) & (v[m].z != 0) & (v[m].w != 0);
                    if (ok) break;
                    __nanosleep(300);
                }
                float4 a = make_float4(0.f, 0.f, 0.f, 0.f);
#pragma unroll
                for (int m = 0; m < 16; m++) { a.x += dec_word(v[m].x); a.y += dec_word(v[m].y); a.z += dec_word(v[m].z); a.w += dec_word(v[m].w); }
                *reinterpret_cast<float4*>(s_cs + at * 4) = a;
            } else if (at >= 64) {
                uint4 u, v;
                const uint32_t* ps = reinterpret_cast<const uint32_t*>(&g_ln1[mb * 128 + lane * 4]);
                for (int it = 0; it < SPIN_LIMIT; it++) {
                    u = ld_relaxed_v4(ps); v = ld_relaxed_v4(ps + 4);
                    if (u.x && u.y && u.z && u.w && v.x && v.y && v.z && v.w) break;
                    __nanosleep(300);
                }
                *reinterpret_cast<float4*>(&s_stat[lane * 4]) = make_float4(dec_word(u.x), dec_word(u.y), dec_word(u.z), dec_word(u.w));
                *reinterpret_cast<float4*>(&s_stat[lane * 4 + 2]) = make_float4(dec_word(v.x), dec_word(v.y), dec_word(v.z), dec_word(v.w));
            }
            __syncwarp();
            STAMP(0, 7, at == 0 && s_cs[0] != 12345.f);
            bar_arrive(1, 352);
        }
    } else {
        float acc[120];
#pragma unroll
        for (int i = 0; i < 120; i++) acc[i] = 0.f;
        int st = 0, ph = 0, pst = 0;
#pragma unroll 1
        for (int kb = 0; kb < 10; kb++) {
            mbar_wait(full + 8 * st, ph);
            STAMP(0, 1, tid == 0 && kb == 0);
            const uint32_t sa = ((sbase + st * K1_STB) & 0x3FFFF) >> 4;
            wg_fence();
#pragma unroll
            for (int j = 0; j < 4; j++) {
                uint64_t da = desc_from(sa + wg * 512 + j * 2 + (1u << 16), DESC_SW128);
                uint64_t db = desc_from(sa + 1024 + j * 128 + ((8192u >> 4) << 16), DESC_SW128);
                wgmma_ss_n240_ta0_tb1(acc, da, db, 1);
            }
            wg_commit();
            if (kb > 0) {
                wg_wait<1>();
                if ((tid & 127) == 0) mbar_arrive(empty + 8 * pst);
            }
            pst = st;
            if (++st == K1_ST) { st = 0; ph ^= 1; }
        }
        wg_wait<0>();
        fence_regs(acc);
        STAMP(0, 2, tid == 0);
        bar_sync(1, 352);
        const int g = lane >> 2, t = lane & 3;
        const float2 st0 = s_stat[wg * 64 + warp * 16 + g], st1 = s_stat[wg * 64 + warp * 16 + g + 8];
        const uint32_t stw = sbase + (wg * 4 + warp) * 9216;
        const uint32_t stg = stw + g * 16;
        const uint32_t o0 = stg + t * 4;
        const uint32_t o2 = stg + (t < 2 ? 256 + t * 4 : 768 + (t - 2) * 4);
        const uint32_t o3 = stg + (t < 2 ? 768 + 8 + t * 4 : 768 + 128 + (t - 2) * 4);
        const int er = lane & 15, eh = lane >> 4;
        const uint32_t ea = stw + eh * 768 + (er >> 3) * 384 + (er & 7) * 16;
        const uint32_t pf = ((POLYMASK >> (warp * 2 + (er >> 3))) & 1) ? 0x3F80u : 0u;
        const int blk = mb * 2 + wg;
        float2 cs[30];
#pragma unroll
        for (int j = 0; j < 5; j++) cs[j] = *reinterpret_cast<const float2*>(s_cs + 2 * t + 8 * j);
#pragma unroll
        for (int hp = 0; hp < 6; hp++) {
            if (hp < 5) {
#pragma unroll
                for (int j = hp * 5 + 5; j < hp * 5 + 10; j++) cs[j] = *reinterpret_cast<const float2*>(s_cs + 2 * t + 8 * j);
            }
            const int gp = nb * 6 + hp, which = gp >> 4, head = (gp & 15) * 2;
            const float qs = which == 0 ? 0.22360679775f * 1.44269504089f : 1.f;
            const float ra = st0.y * qs, rb = st1.y * qs, ma = -st0.x * ra, mc = -st1.x * rb;
#pragma unroll
            for (int i = 0; i < 5; i++) {
                const int j = hp * 5 + i;
                const uint32_t v0 = pack_bf16(fmaf(acc[4 * j], ra, ma * cs[j].x), fmaf(acc[4 * j + 1], ra, ma * cs[j].y));
                const uint32_t v1 = pack_bf16(fmaf(acc[4 * j + 2], rb, mc * cs[j].x), fmaf(acc[4 * j + 3], rb, mc * cs[j].y));
                const uint32_t dst = hp * 1536 + (i == 0 ? o0 : i == 1 ? o0 + 128 : i == 2 ? o2 : i == 3 ? o3 : o3 + 128);
                sts32(dst, v0);
                sts32(dst + 384, v1);
            }
            const uint32_t f = which == 1 ? pf : 0u;
            asm volatile("st.shared.v2.b32 [%0], {%1, %2};" :: "r"(ea + hp * 1536 + 256 + 8), "r"(0x3F80u | (f << 16)), "r"(f | (f << 16)) : "memory");
            __syncwarp();
            uint8_t* dst = (which == 0 ? g_q + (head * 32 + blk) * 3072 : g_kv + (head * 32 + blk) * 6144 + (which - 1) * 3072) + warp * 768;
            const int hs = which == 0 ? 32 * 3072 : 32 * 6144;
#pragma unroll
            for (int i = 0; i < 3; i++) {
                const int pc = i * 32 + lane;
                uint4 u;
                asm volatile("ld.shared.v4.b32 {%0, %1, %2, %3}, [%4];" : "=r"(u.x), "=r"(u.y), "=r"(u.z), "=r"(u.w) : "r"(stw + hp * 1536 + pc * 16));
                *reinterpret_cast<uint4*>(dst + (pc >= 48 ? hs + (pc - 48) * 16 : pc * 16)) = u;
            }
            STAMP(0, 5, tid == 0 && hp == 0);
            if (which == 1) {
                const uint32_t a = ea + hp * 1536;
                uint4 u, v; uint2 w;
                asm volatile("ld.shared.v4.b32 {%0, %1, %2, %3}, [%4];" : "=r"(u.x), "=r"(u.y), "=r"(u.z), "=r"(u.w) : "r"(a));
                asm volatile("ld.shared.v4.b32 {%0, %1, %2, %3}, [%4];" : "=r"(v.x), "=r"(v.y), "=r"(v.z), "=r"(v.w) : "r"(a + 128));
                asm volatile("ld.shared.v2.b32 {%0, %1}, [%2];" : "=r"(w.x), "=r"(w.y) : "r"(a + 256));
                uint32_t c0 = hfma2(u.x, u.x, 0u), c1 = hfma2(u.y, u.y, 0u);
                c0 = hfma2(u.z, u.z, c0); c1 = hfma2(u.w, u.w, c1);
                c0 = hfma2(v.x, v.x, c0); c1 = hfma2(v.y, v.y, c1);
                c0 = hfma2(v.z, v.z, c0); c1 = hfma2(v.w, v.w, c1);
                c0 = hfma2(w.x, w.x, c0); c1 = hfma2(w.y, w.y, c1);
                const float n2 = (bf_lo(c0) + bf_hi(c0)) + (bf_lo(c1) + bf_hi(c1));
                const uint32_t nb2 = __float_as_uint(n2) & 0x7fffffffu;
                const uint32_t m0 = __reduce_max_sync(~0u, eh ? 0u : nb2), m1 = __reduce_max_sync(~0u, eh ? nb2 : 0u);
                if (er == 0) g_kn2[(head + eh) * 128 + blk * 4 + warp] = __uint_as_float(eh ? m1 : m0);
            }
        }
        STAMP(0, 6, tid == 0);
        STAMP(0, 4, tid == 0);
    }
}

constexpr int K2_KV = 32 * 6144, K2_SMEM = K2_KV + 24576;
constexpr int K2_NLD = 8;

__device__ __forceinline__ uint32_t exp2_pair(float y0, float y1, uint32_t kHalf, uint32_t kLow) {
    uint32_t sp = __byte_perm(__float_as_uint(y0), __float_as_uint(y1), 0x6521);
    uint32_t m, e;
    asm("lop3.b32 %0, %1, 0x807F807F, %2, 0xEA;" : "=r"(m) : "r"(sp), "r"(kHalf));
    asm("lop3.b32 %0, %1, 0x7F807F80, %2, 0xEA;" : "=r"(e) : "r"(sp), "r"(kLow));
    return hfma2(sp, m, e);
}

__global__ void __launch_bounds__(512, 1) attn_kernel(const __nv_bfloat16* __restrict__ wo, const __nv_bfloat16* __restrict__ w1,
                                                      const __nv_bfloat16* __restrict__ w2, uint32_t kHalf, uint32_t kLow, uint32_t kZero, uint32_t kZero2, uint32_t kStep) {
    extern __shared__ __align__(1024) uint8_t smem[];
    __shared__ __align__(8) uint64_t bars[K2_NLD + 1];
    const int tid = threadIdx.x, wg = __shfl_sync(~0u, tid >> 7, 0), warp = __shfl_sync(~0u, (tid >> 5) & 3, 0), lane = tid & 31, g = lane >> 2, t = lane & 3;
    if (blockIdx.x >= 128) {
        pdl_launch();
        const int hb = blockIdx.x - 128;
        for (int i = hb * 512 + tid; i < D * 80; i += 4 * 512) {
            const int k = i / 80, c = i % 80;
            const uint4 v = __ldg(reinterpret_cast<const uint4*>(wo + (size_t)k * D) + c);
            *reinterpret_cast<uint4*>(g_wo + ((c / 20) * 80 + (k >> 3)) * 2560 + (c % 20) * 128 + (k & 7) * 16) = v;
        }
        return;
    }
    STAMP(1, 0, tid == 0);
    const int head = blockIdx.x >> 2, qq = blockIdx.x & 3;
    const uint32_t sbase = smem_u32(smem), bbase = smem_u32(bars);
    constexpr int LDB = K2_KV / K2_NLD;
    if (tid == 0) {
        for (int i = 0; i <= K2_NLD; i++) mbar_init(bbase + 8 * i, 1);
        fence_mbar_init();
    }
    __syncthreads();
    pdl_launch();
    const uint8_t* kvsrc = g_kv + (size_t)head * K2_KV;
    const uint8_t* qsrc = g_q + (head * 32 + qq * 8) * 3072;
    if (wg == 3 && warp == 0) {
        if (elect_one()) {
            mbar_expect_tx(bbase + 8 * K2_NLD, 12288 + 6144);
            pdl_wait();
            bulk_load(sbase + K2_KV, qsrc, 12288, bbase + 8 * K2_NLD);
            bulk_load(sbase, kvsrc, 6144, bbase + 8 * K2_NLD);
        }
        __syncwarp();
    }
    pdl_wait();
    STAMP(1, 1, tid == 0);
    const uint4 kq = __ldcg(reinterpret_cast<const uint4*>(g_kn2 + head * 128) + lane);
    if (wg == 3 && warp == 0) {
        if (elect_one()) {
            mbar_wait(bbase + 8 * K2_NLD, 0);
            mbar_expect_tx(bbase, LDB - 6144);
            bulk_load(sbase + 6144, kvsrc + 6144, LDB - 6144, bbase);
#pragma unroll 1
            for (int c = 1; c < K2_NLD; c++) {
                mbar_expect_tx(bbase + 8 * c, c == K2_NLD - 1 ? LDB + 12288 : LDB);
                bulk_load(sbase + c * LDB, kvsrc + c * LDB, LDB, bbase + 8 * c);
            }
            bulk_load(sbase + K2_KV + 12288, qsrc + 12288, 12288, bbase + 8 * (K2_NLD - 1));
        }
        __syncwarp();
    }
    const float kn2 = __uint_as_float(__reduce_max_sync(~0u, max(max(kq.x, kq.y), max(kq.z, kq.w)))) * 1.05f;
    const uint32_t dbase = (sbase & 0x3FFFF) >> 4;
    kHalf = __shfl_sync(~0u, kHalf, 0); kLow = __shfl_sync(~0u, kLow, 1);
    const uint32_t qz2 = __shfl_sync(~0u, kZero, 2), qz3 = __shfl_sync(~0u, kZero2, 3);

#pragma unroll 1
    for (int tl = 0; tl < 2; tl++) {
        mbar_wait(bbase + 8 * K2_NLD, 0);
        const uint32_t* qp = reinterpret_cast<const uint32_t*>(smem + K2_KV + (tl * 4 + wg) * 3072 + warp * 768) + lane;
        uint32_t qa0 = qp[0], qa1 = qp[96], qa2 = qp[32], qa3 = qp[128];
        uint32_t qb0 = t < 2 ? qp[64] : 0u, qb1 = t < 2 ? qp[160] : 0u;
        auto sq2 = [](uint32_t v) { float a = bf_lo(v), c = bf_hi(v); return a * a + c * c; };
        float n0 = sq2(qa0) + sq2(qa2) + sq2(qb0), n1 = sq2(qa1) + sq2(qa3) + sq2(qb1);
        n0 += __shfl_xor_sync(~0u, n0, 1); n1 += __shfl_xor_sync(~0u, n1, 1);
        n0 += __shfl_xor_sync(~0u, n0, 2); n1 += __shfl_xor_sync(~0u, n1, 2);
        STAMP(1, 5, tid == 0 && tl == 0 && n0 != 1.2345f);
        const float m0 = ceilf(sqrt_fast(n0 * kn2) * 1.001f), m1 = ceilf(sqrt_fast(n1 * kn2) * 1.001f);
        uint32_t unsafe;
        {
            const uint32_t bad = !(m0 <= 48.f && m1 <= 48.f);
            asm volatile("{\n.reg .pred p, q;\nsetp.ne.u32 p, %1, 0;\nbarrier.red.or.pred.aligned q, %2, 128, p;\nselp.u32 %0, 1, 0, q;\n}\n" : "=r"(unsafe) : "r"(bad), "r"(wg + 1) : "memory");
            unsafe = __shfl_sync(~0u, unsafe, 0);
        }
        float oacc[12];
#pragma unroll
        for (int i = 0; i < 12; i++) oacc[i] = 0.f;
        float sacc[32];
        uint32_t p[16], p2[16];
#pragma unroll
        for (int i = 0; i < 32; i++) sacc[i] = 0.f;
        uint64_t dk0 = desc_from(dbase + ((128 >> 4) << 16), 384 >> 4);
        uint64_t dk1 = desc_from(dbase + (256 >> 4), 384 >> 4);
        uint64_t dv[4];
#pragma unroll
        for (int kk = 0; kk < 4; kk++) dv[kk] = desc_from(dbase + (3072 >> 4) + kk * 48 + ((384 >> 4) << 16), 128 >> 4);
        auto qk = [&]() {
            wgmma_rs_n64_tb0(sacc, qa0, qa1, qa2, qa3, dk0, 0);
            wgmma_rs_n64_tb0(sacc, qb0, qb1, qz2, qz3, dk1, 1);
            desc_adv(dk0, kStep); desc_adv(dk1, kStep);
        };
        auto pv = [&](uint32_t (&p)[16]) {
#pragma unroll
            for (int kk = 0; kk < 4; kk++) {
                wgmma_rs_n24_tb1(oacc, p[4 * kk], p[4 * kk + 1], p[4 * kk + 2], p[4 * kk + 3], dv[kk], 1);
                desc_adv(dv[kk], kStep);
            }
        };
        if (!unsafe) {
            if (t == 2) { qb0 = pack_bf16(-m0, 384.f); qb1 = pack_bf16(-m1, 384.f); }
            if (t == 3) { qb0 = pack_bf16(-1.5859375f, -0.0020625f); qb1 = qb0; }
            auto softmax = [&](uint32_t (&p)[16]) {
                fence_regs(sacc);
#pragma unroll
                for (int gi = 0; gi < 8; gi++) {
                    if ((POLYMASK >> gi) & 1) {
                        p[2 * gi] = exp2_pair(sacc[4 * gi], sacc[4 * gi + 1], kHalf, kLow);
                        p[2 * gi + 1] = exp2_pair(sacc[4 * gi + 2], sacc[4 * gi + 3], kHalf, kLow);
                    } else {
                        p[2 * gi] = pack_bf16(ex2f(sacc[4 * gi]), ex2f(sacc[4 * gi + 1]));
                        p[2 * gi + 1] = pack_bf16(ex2f(sacc[4 * gi + 2]), ex2f(sacc[4 * gi + 3]));
                    }
                }
                fence_regs(p);
            };
            STAMP(1, 6, tid == 0 && tl == 0);
            STAMP(1, 2, tid == 0 && tl == 0);
            wg_fence(); qk(); wg_commit(); wg_wait<0>();
            softmax(p);
            mbar_wait(bbase, 0);
#pragma unroll 1
            for (int c = 0; c < K2_NLD; c++) {
                wg_fence(); qk(); wg_commit(); pv(p); wg_commit(); wg_wait<1>();
                softmax(p2);
                wg_fence(); qk(); wg_commit(); pv(p2); wg_commit(); wg_wait<1>();
                softmax(p);
                wg_fence(); qk(); wg_commit(); pv(p); wg_commit(); wg_wait<1>();
                softmax(p2);
                if (c == K2_NLD - 1) break;
                mbar_wait(bbase + 8 * (c + 1), 0);
                wg_fence(); qk(); wg_commit(); pv(p2); wg_commit(); wg_wait<1>();
                softmax(p);
            }
            wg_fence(); pv(p2); wg_commit(); wg_wait<0>();
        } else {
            float mx0 = -INFINITY, mx1 = -INFINITY;
#pragma unroll 1
            for (int j = 0; j < 32; j++) {
                mbar_wait(bbase + 8 * (j >> 2), 0);
                wg_fence(); qk(); wg_commit(); wg_wait<0>();
                fence_regs(sacc);
                float a = mx0, c = mx1;
#pragma unroll
                for (int gi = 0; gi < 8; gi++) {
                    a = fmaxf(a, fmaxf(sacc[4 * gi], sacc[4 * gi + 1]));
                    c = fmaxf(c, fmaxf(sacc[4 * gi + 2], sacc[4 * gi + 3]));
                }
                a = fmaxf(a, __shfl_xor_sync(~0u, a, 1)); c = fmaxf(c, __shfl_xor_sync(~0u, c, 1));
                a = fmaxf(a, __shfl_xor_sync(~0u, a, 2)); c = fmaxf(c, __shfl_xor_sync(~0u, c, 2));
                const float s0 = ex2f(mx0 - a), s1 = ex2f(mx1 - c);
                mx0 = a; mx1 = c;
#pragma unroll
                for (int gi = 0; gi < 3; gi++) { oacc[4 * gi] *= s0; oacc[4 * gi + 1] *= s0; oacc[4 * gi + 2] *= s1; oacc[4 * gi + 3] *= s1; }
#pragma unroll
                for (int gi = 0; gi < 8; gi++) {
                    p[2 * gi] = pack_bf16(ex2f(sacc[4 * gi] - a), ex2f(sacc[4 * gi + 1] - a));
                    p[2 * gi + 1] = pack_bf16(ex2f(sacc[4 * gi + 2] - c), ex2f(sacc[4 * gi + 3] - c));
                }
                fence_regs(p); fence_regs(oacc);
                wg_fence(); pv(p); wg_commit(); wg_wait<0>();
                fence_regs(oacc);
            }
        }
        fence_regs(oacc);
        const float l0 = __shfl_sync(~0u, oacc[8], (lane & ~3) | 2), l1 = __shfl_sync(~0u, oacc[10], (lane & ~3) | 2);
        const float r0 = __fdividef(1.f, l0), r1 = __fdividef(1.f, l1);
        uint8_t* ob = g_o + (qq * 8 + tl * 4 + wg) * 81920 + warp * 256 + g * 16;
#pragma unroll
        for (int gi = 0; gi < 3; gi++) {
            if (gi < 2 || t < 2) {
                const int c = head * 20 + gi * 8 + 2 * t;
                uint8_t* dst = ob + (c >> 3) * 1024 + (c & 7) * 2;
                *reinterpret_cast<uint32_t*>(dst) = pack_bf16(oacc[4 * gi] * r0, oacc[4 * gi + 1] * r0);
                *reinterpret_cast<uint32_t*>(dst + 128) = pack_bf16(oacc[4 * gi + 2] * r1, oacc[4 * gi + 3] * r1);
            }
        }
        STAMP(1, 3 + tl, tid == 0);
        if (tl == 0 && warp == 1) {
            constexpr int PB = S * F * 2 / 256;
            if (elect_one()) l2_prefetch(reinterpret_cast<const uint8_t*>(wg & 1 ? w2 : w1) + (size_t)(blockIdx.x * 2 + (wg >> 1)) * PB, PB);
            __syncwarp();
        }
    }
}

constexpr int G_ST = 7, G_STB = 8192 + 20480;
constexpr int G_SMEM = G_ST * G_STB + 20480 + 1024;

constexpr int NCW = 2, NJ = 10;
struct Ring { int st, ph; __device__ __forceinline__ void next() { if (++st == G_ST) { st = 0; ph ^= 1; } } };

template <int TA, int NKB, typename Tail>
__device__ __forceinline__ void gemm_loop(float (&acc)[NJ * 4], Ring& r, uint32_t sbase, uint32_t full, uint32_t empty, int wg, int tid, Tail tail) {
    int pst = 0;
    fence_regs(acc);
#pragma unroll 1
    for (int kb = 0; kb < NKB; kb++) {
        mbar_wait(full + 8 * r.st, r.ph);
        STAMP(NKB == 10 ? 2 : (NKB == 32 ? 3 : 4), 2, tid == 0 && kb == 0);
        const uint32_t sa = ((sbase + r.st * G_STB) & 0x3FFFF) >> 4;
        wg_fence();
#pragma unroll
        for (int j = 0; j < 4; j++) {
            const uint64_t db = desc_from(sa + 512 + wg * 80 + j * 320 + ((2560u >> 4) << 16), 128 >> 4);
            if (TA == 0) wgmma_ss_n80_ta0_tb1(acc, desc_from(sa + j * 128 + ((1024u >> 4) << 16), 128 >> 4), db, 1);
            else wgmma_ss_n80_ta1_tb1(acc, desc_from(sa + j * 128 + (1u << 16), DESC_SW128), db, 1);
        }
        wg_commit();
        if (kb > 0) {
            wg_wait<1>();
            if ((tid & 127) == 0) mbar_arrive(empty + 8 * pst);
        }
        pst = r.st;
        r.next();
    }
    tail();
    wg_wait<0>();
    if ((tid & 127) == 0) mbar_arrive(empty + 8 * pst);
    fence_regs(acc);
}

__device__ __forceinline__ void publish(int* cnt, int tid) {
    bar_sync(2, NCW * 128);
    asm volatile("{\n.reg .pred p;\nsetp.eq.u32 p, %1, 0;\n@p red.release.gpu.global.add.s32 [%0], 1;\n}\n" :: "l"(cnt), "r"(tid) : "memory");
}

__global__ void __cluster_dims__(2, 1, 1) __launch_bounds__(NCW * 128 + 64, 1) tail_kernel(const __grid_constant__ CUtensorMap tmX, const __grid_constant__ CUtensorMap tmW1,
                                                      const __grid_constant__ CUtensorMap tmW2, const __grid_constant__ CUtensorMap tmOut,
                                                      const __nv_bfloat16* __restrict__ b1p, const __nv_bfloat16* __restrict__ b2p) {
    extern __shared__ uint8_t smem_raw[];
    __shared__ __align__(8) uint64_t bars[2 * G_ST + 1];
    const uint32_t sbase = (smem_u32(smem_raw) + 1023) & ~1023u;
    const uint32_t sio = sbase + G_ST * G_STB;
    const uint32_t full = smem_u32(bars), empty = full + 8 * G_ST, xbar = full + 16 * G_ST;
    const int tid = threadIdx.x, wid = __shfl_sync(~0u, tid >> 5, 0), lane = tid & 31;
    const int mt = blockIdx.x >> 2, nt = blockIdx.x & 3;
    const bool has_up = mt < 27;
    STAMP(2, 0, tid == 0);
    if (tid == 0) {
        for (int i = 0; i < G_ST; i++) { mbar_init(full + 8 * i, 2); mbar_init(empty + 8 * i, NCW); }
        mbar_init(xbar, 1);
        fence_mbar_init();
    }
    __syncthreads();
    if (wid == NCW * 4) {
        if (elect_one()) {
            mbar_expect_tx(xbar, 20480);
            tma2d(sio, &tmX, nt * 160, mt * 64, xbar);
            prefetch_tmap(&tmW1); prefetch_tmap(&tmW2); prefetch_tmap(&tmOut);
            pdl_wait();
            Ring r{0, 1};
            const int n1 = has_up ? 42 : 10;
#pragma unroll 1
            for (int i = 0; i < n1 + 27; i++) {
                const uint32_t sa = sbase + r.st * G_STB, fb = full + 8 * r.st;
                mbar_wait(empty + 8 * r.st, r.ph);
                mbar_expect_tx(fb, 8192);
                if (i < 10) bulk_load(sa, g_o + (size_t)mt * 81920 + i * 8192, 8192, fb);
                else if (i < n1) tma2d(sa, &tmW1, mt * 64, (i - 10) * 64, fb);
                else tma2d(sa, &tmW2, mt * 64, (i - n1) * 64, fb);
                r.next();
            }
        }
    } else if (wid == NCW * 4 + 1) {
        if (elect_one()) {
            pdl_wait();
            Ring r{0, 1};
            const int n1 = has_up ? 42 : 10;
            const uint8_t* src = g_wo + (size_t)nt * 10 * 20480;
#pragma unroll 1
            for (int i = 0; i < n1 + 27; i++) {
                if (i == 10 || i == n1) {
                    const bool down = i == n1;
                    const int* cnt = down ? &g_cnt[nt * 64 + 32] : &g_cnt[nt * 64];
                    const int need = down ? 27 : 32;
#pragma unroll 1
                    for (int it = 0; it < SPIN_LIMIT && ld_acquire(cnt) < need; it++) {}
                    asm volatile("fence.proxy.async;" ::: "memory");
                    src = down ? g_g + (size_t)nt * 27 * 20480 : g_hn + (size_t)nt * 32 * 20480;
                    STAMP(down ? 4 : 3, 6, true);
                }
                mbar_wait(empty + 8 * r.st, r.ph);
                mbar_expect_tx(full + 8 * r.st, 20480);
                bulk_load(sbase + r.st * G_STB + 8192, src, 20480, full + 8 * r.st);
                src += 20480;
                r.next();
            }
        }
    } else {
        const int wg = wid >> 2, warp = wid & 3, g = lane >> 2, t = lane & 3;
        const int row = mt * 64 + warp * 16 + g;
        uint32_t braw[4];
        {
            const int rowu = has_up ? row : 0;
            asm volatile("ld.global.nc.u16 %0, [%1];" : "=r"(braw[0]) : "l"(b1p + rowu));
            asm volatile("ld.global.nc.u16 %0, [%1];" : "=r"(braw[1]) : "l"(b1p + rowu + 8));
            asm volatile("ld.global.nc.u16 %0, [%1];" : "=r"(braw[2]) : "l"(b2p + row));
            asm volatile("ld.global.nc.u16 %0, [%1];" : "=r"(braw[3]) : "l"(b2p + row + 8));
        }
        const uint32_t ioa = sio + (warp * 16 + g) * 320 + wg * 160 + t * 4;
        uint32_t hp[NJ * 2];
        pdl_wait();
        STAMP(2, 1, tid == 0);
        if (tid < 60) *reinterpret_cast<uint4*>(g_cs + blockIdx.x * 240 + tid * 4) = make_uint4(0u, 0u, 0u, 0u);
        else if (tid < 76) g_ln1[blockIdx.x * 16 + tid - 60] = make_uint2(0u, 0u);
        float acc[NJ * 4];
#pragma unroll
        for (int i = 0; i < NJ * 4; i++) acc[i] = 0.f;
        Ring r{0, 0};
        gemm_loop<0, 10>(acc, r, sbase, full, empty, wg, tid, [&]() {
            mbar_wait(xbar, 0);
#pragma unroll
            for (int j = 0; j < NJ; j++) {
                asm volatile("ld.shared.b32 %0, [%1];" : "=r"(hp[2 * j]) : "r"(ioa + j * 16));
                asm volatile("ld.shared.b32 %0, [%1];" : "=r"(hp[2 * j + 1]) : "r"(ioa + j * 16 + 2560));
            }
        });
        STAMP(2, 3, tid == 0);
        {
            float s0 = 0.f, q0 = 0.f, s1 = 0.f, q1 = 0.f;
#pragma unroll
            for (int j = 0; j < NJ; j++) {
                const uint32_t h0 = pack_bf16(acc[4 * j] + bf_lo(hp[2 * j]), acc[4 * j + 1] + bf_hi(hp[2 * j]));
                const uint32_t h1 = pack_bf16(acc[4 * j + 2] + bf_lo(hp[2 * j + 1]), acc[4 * j + 3] + bf_hi(hp[2 * j + 1]));
                hp[2 * j] = h0; hp[2 * j + 1] = h1;
                const float a = bf_lo(h0), c = bf_hi(h0), e = bf_lo(h1), f = bf_hi(h1);
                s0 += a + c; q0 = fmaf(a, a, fmaf(c, c, q0)); s1 += e + f; q1 = fmaf(e, e, fmaf(f, f, q1));
            }
            s0 += __shfl_xor_sync(~0u, s0, 1); q0 += __shfl_xor_sync(~0u, q0, 1); s1 += __shfl_xor_sync(~0u, s1, 1); q1 += __shfl_xor_sync(~0u, q1, 1);
            s0 += __shfl_xor_sync(~0u, s0, 2); q0 += __shfl_xor_sync(~0u, q0, 2); s1 += __shfl_xor_sync(~0u, s1, 2); q1 += __shfl_xor_sync(~0u, q1, 2);
            uint2* xs = g_ln2 + (mt * 4 + warp) * 64 * NCW;
            if (t < 2) st_relaxed_v2(xs + wg * 64 + nt * 16 + g * 2 + t, __float_as_uint(t ? s1 : s0), __float_as_uint(t ? q1 : q0) | 0x80000000u);
            STAMP(2, 5, tid == 0);
            uint4 u, u2;
            int it = 0;
#pragma unroll 1
            do {
                u = ld_relaxed_2x64(xs + t * 16 + g * 2);
                u2 = ld_relaxed_2x64(xs + 64 + t * 16 + g * 2);
            } while (!__all_sync(~0u, (u.y & u.w & u2.y & u2.w) >> 31) && ++it < SPIN_LIMIT);
            s0 = __uint_as_float(u.x) + __uint_as_float(u2.x); q0 = -(__uint_as_float(u.y) + __uint_as_float(u2.y));
            s1 = __uint_as_float(u.z) + __uint_as_float(u2.z); q1 = -(__uint_as_float(u.w) + __uint_as_float(u2.w));
            s0 += __shfl_xor_sync(~0u, s0, 1); q0 += __shfl_xor_sync(~0u, q0, 1); s1 += __shfl_xor_sync(~0u, s1, 1); q1 += __shfl_xor_sync(~0u, q1, 1);
            s0 += __shfl_xor_sync(~0u, s0, 2); q0 += __shfl_xor_sync(~0u, q0, 2); s1 += __shfl_xor_sync(~0u, s1, 2); q1 += __shfl_xor_sync(~0u, q1, 2);
            STAMP(2, 7, tid == 0 && s0 != 1.2345f);
            const float mu0 = s0 * (1.f / D), mu1 = s1 * (1.f / D);
            const float v0 = fmaxf(q0 * (1.f / D) - mu0 * mu0, 0.f), v1 = fmaxf(q1 * (1.f / D) - mu1 * mu1, 0.f);
            float ra = rsqrtf(v0 + LN_EPS), rb = rsqrtf(v1 + LN_EPS);
            ra *= rsqrtf(v0 * ra * ra + LN_EPS); rb *= rsqrtf(v1 * rb * rb + LN_EPS);
            const float ca = -mu0 * ra, cb = -mu1 * rb;
            uint32_t* dst = reinterpret_cast<uint32_t*>(g_hn + ((size_t)nt * 256 + mt * 8 + warp * 2) * 2560 + wg * 1280) + lane;
#pragma unroll
            for (int j = 0; j < NJ; j++) {
                dst[j * 32] = pack_bf16(fmaf(bf_lo(hp[2 * j]), ra, ca), fmaf(bf_hi(hp[2 * j]), ra, ca));
                dst[j * 32 + 640] = pack_bf16(fmaf(bf_lo(hp[2 * j + 1]), rb, cb), fmaf(bf_hi(hp[2 * j + 1]), rb, cb));
            }
            STAMP(3, 7, tid == 0);
            publish(&g_cnt[nt * 64], tid);
        }
        STAMP(2, 4, tid == 0);
        if (has_up) {
            fence_regs(braw);
#pragma unroll
            for (int j = 0; j < NJ; j++) { acc[4 * j] = acc[4 * j + 1] = bf_lo(braw[0]); acc[4 * j + 2] = acc[4 * j + 3] = bf_lo(braw[1]); }
            gemm_loop<1, 32>(acc, r, sbase, full, empty, wg, tid, []() {});
            STAMP(3, 3, tid == 0);
            auto gelu = [](float u) { const float hu = 0.5f * u; return fmaf(hu, tanhf_fast(u * fmaf(u * u, 0.0356774081f, 0.7978845608f)), hu); };
            uint32_t* dst = reinterpret_cast<uint32_t*>(g_g + ((size_t)nt * 216 + mt * 8 + warp * 2) * 2560 + wg * 1280) + lane;
#pragma unroll
            for (int j = 0; j < NJ; j++) {
                dst[j * 32] = pack_bf16(gelu(acc[4 * j]), gelu(acc[4 * j + 1]));
                dst[j * 32 + 640] = pack_bf16(gelu(acc[4 * j + 2]), gelu(acc[4 * j + 3]));
            }
            STAMP(3, 5, tid == 0);
            publish(&g_cnt[nt * 64 + 32], tid);
            STAMP(3, 4, tid == 0);
        }
        fence_regs(braw);
        const float bd0 = bf_lo(braw[2]), bd1 = bf_lo(braw[3]);
#pragma unroll
        for (int j = 0; j < NJ; j++) {
            acc[4 * j] = bd0 + bf_lo(hp[2 * j]); acc[4 * j + 1] = bd0 + bf_hi(hp[2 * j]);
            acc[4 * j + 2] = bd1 + bf_lo(hp[2 * j + 1]); acc[4 * j + 3] = bd1 + bf_hi(hp[2 * j + 1]);
        }
        gemm_loop<1, 27>(acc, r, sbase, full, empty, wg, tid, []() {});
        STAMP(4, 3, tid == 0);
        const uint32_t ow = sio + wid * (16 * NJ * 16), oa = ow + g * (NJ * 16) + t * 4;
#pragma unroll
        for (int j = 0; j < NJ; j++) {
            sts32(oa + j * 16, pack_bf16(acc[4 * j], acc[4 * j + 1]));
            sts32(oa + j * 16 + 8 * NJ * 16, pack_bf16(acc[4 * j + 2], acc[4 * j + 3]));
        }
        fence_async_smem();
        __syncwarp();
        if (elect_one()) {
            tma2d_store(&tmOut, ow, nt * 160 + wg * 80, mt * 64 + warp * 16);
            asm volatile("cp.async.bulk.commit_group;\ncp.async.bulk.wait_group.read 0;" ::: "memory");
        }
        STAMP(4, 4, tid == 0);
    }
}

typedef CUresult (*EncFn)(CUtensorMap*, CUtensorMapDataType, cuuint32_t, void*, const cuuint64_t*, const cuuint64_t*, const cuuint32_t*,
                          const cuuint32_t*, CUtensorMapInterleave, CUtensorMapSwizzle, CUtensorMapL2promotion, CUtensorMapFloatOOBfill);

CUtensorMap make_map(EncFn enc, const void* p, int rows, int cols, int box_rows, int box_cols, CUtensorMapSwizzle sw) {
    CUtensorMap m;
    cuuint64_t dims[2] = {(cuuint64_t)cols, (cuuint64_t)rows};
    cuuint64_t str[1] = {(cuuint64_t)cols * 2};
    cuuint32_t box[2] = {(cuuint32_t)box_cols, (cuuint32_t)box_rows}, es[2] = {1, 1};
    enc(&m, CU_TENSOR_MAP_DATA_TYPE_BFLOAT16, 2, const_cast<void*>(p), dims, str, box, es, CU_TENSOR_MAP_INTERLEAVE_NONE, sw,
        CU_TENSOR_MAP_L2_PROMOTION_L2_128B, CU_TENSOR_MAP_FLOAT_OOB_FILL_NONE);
    return m;
}

template <typename... KArgs, typename... Args>
void launch(void (*k)(KArgs...), int grid, int block, int smem, bool pdl, Args... args) {
    cudaLaunchConfig_t cfg = {};
    cfg.gridDim = dim3(grid); cfg.blockDim = dim3(block); cfg.dynamicSmemBytes = smem; cfg.stream = cudaStreamPerThread;
    cudaLaunchAttribute at[1];
    at[0].id = cudaLaunchAttributeProgrammaticStreamSerialization; at[0].val.programmaticStreamSerializationAllowed = 1;
    cfg.attrs = at; cfg.numAttrs = pdl ? 1 : 0;
    cudaLaunchKernelEx(&cfg, k, KArgs(args)...);
}

}

extern "C" void kernel_launch(void* const* d_in, const int* in_sizes, int n_in, void* d_out, int out_size) {
    const __nv_bfloat16* x = (const __nv_bfloat16*)d_in[0];
    const __nv_bfloat16* wqkv = (const __nv_bfloat16*)d_in[1];
    const __nv_bfloat16* wo = (const __nv_bfloat16*)d_in[2];
    const __nv_bfloat16* w1 = (const __nv_bfloat16*)d_in[4];
    const __nv_bfloat16* b1 = (const __nv_bfloat16*)d_in[5];
    const __nv_bfloat16* w2 = (const __nv_bfloat16*)d_in[6];
    const __nv_bfloat16* b2 = (const __nv_bfloat16*)d_in[7];
    static EncFn enc = nullptr;
    if (!enc) {
        cudaDriverEntryPointQueryResult qr;
        cudaGetDriverEntryPoint("cuTensorMapEncodeTiled", (void**)&enc, cudaEnableDefault, &qr);
        cudaFuncSetAttribute(qkv_kernel, cudaFuncAttributeMaxDynamicSharedMemorySize, K1_SMEM);
        cudaFuncSetAttribute(attn_kernel, cudaFuncAttributeMaxDynamicSharedMemorySize, K2_SMEM);
        cudaFuncSetAttribute(tail_kernel, cudaFuncAttributeMaxDynamicSharedMemorySize, G_SMEM);
    }
    const CUtensorMap tmX = make_map(enc, x, S, D, 128, 64, CU_TENSOR_MAP_SWIZZLE_128B);
    const CUtensorMap tmW = make_map(enc, wqkv, D, N3, 64, 64, CU_TENSOR_MAP_SWIZZLE_128B);
    const CUtensorMap tmXr = make_map(enc, x, S, D, 64, 160, CU_TENSOR_MAP_SWIZZLE_NONE);
    const CUtensorMap tmW1 = make_map(enc, w1, S, F, 64, 64, CU_TENSOR_MAP_SWIZZLE_128B);
    const CUtensorMap tmW2 = make_map(enc, w2, F, S, 64, 64, CU_TENSOR_MAP_SWIZZLE_128B);
    const CUtensorMap tmOut = make_map(enc, d_out, S, D, 16, 160 / NCW, CU_TENSOR_MAP_SWIZZLE_NONE);
    const bool pdl = true;
    launch(qkv_kernel, 128, 384, K1_SMEM, false, tmX, tmW, x, wqkv);
    launch(attn_kernel, 132, 512, K2_SMEM, pdl, wo, w1, w2, 0x3F003F00u, 0x00010001u, 0u, 0u, 384u);
    launch(tail_kernel, 128, NCW * 128 + 64, G_SMEM, pdl, tmXr, tmW1, tmW2, tmOut, b1, b2);
}
```
